```python
import torch

def _softmax(x, axis=-1):
    return torch.softmax(x, dim=axis)
def _gelu(x):
    return torch.nn.functional.gelu(x, approximate="tanh")
def _silu(x):
    return torch.nn.functional.silu(x)
def _sigmoid(x):
    return torch.sigmoid(x)
def _layernorm(x, axis=-1, eps=1e-5):
    m = x.mean(dim=axis, keepdim=True)
    v = x.var(dim=axis, keepdim=True, unbiased=False)
    return (x - m) / torch.sqrt(v + eps)
def _scatter_add(tgt, idx, src, axis=0):
    return tgt.clone().index_add_(axis, idx, src)
def _segment_sum(src, seg, n):
    out = torch.zeros((n,) + src.shape[1:], dtype=src.dtype)
    return out.index_add_(0, seg, src)
def _pad(x, pw):
    flat = tuple(v for pair in reversed(pw) for v in pair)
    return torch.nn.functional.pad(x, flat)

kernel_name = 'parallel_sum__linear_attn_block__glu_gated_bilinear__prompt'

def setup_inputs():

    _w = (lambda a: (lambda t: t.to(torch.bfloat16) if t.is_floating_point() else t)(torch.as_tensor(a)))
    def _A_setup():
        B, S, D = 1, 2048, 512
        return {
            "x": _w((lambda *s: torch.randn(*s, dtype=torch.bfloat16) * 0.05)(B, S, D)),
            "wqkv": _w((lambda *s: torch.randn(*s, dtype=torch.bfloat16) * 0.05)(D, 3 * D)),
            "wo": _w((lambda *s: torch.randn(*s, dtype=torch.bfloat16) * 0.05)(D, D)),
        }
    _A_in = _A_setup()

    def _B_setup():
        B, S, D, F = 1, 2048, 512, 1792
        return {
            "x": _w((lambda *s: torch.randn(*s, dtype=torch.bfloat16) * 0.05)(B, S, D)),
            "w_gate": _w((lambda *s: torch.randn(*s, dtype=torch.bfloat16) * 0.2)(D, F) * (D ** -0.5)),
            "w_up": _w((lambda *s: torch.randn(*s, dtype=torch.bfloat16) * 0.2)(D, F) * (D ** -0.5)),
            "w_down": _w((lambda *s: torch.randn(*s, dtype=torch.bfloat16) * 0.2)(F, D) * (F ** -0.5)),
        }
    _B_in = _B_setup()

    return {
        "A_x": _A_in["x"],
        "A_wqkv": _A_in["wqkv"],
        "A_wo": _A_in["wo"],
        "B_x": _B_in["x"],
        "B_w_gate": _B_in["w_gate"],
        "B_w_up": _B_in["w_up"],
        "B_w_down": _B_in["w_down"],
    }

def reference(A_x, A_wqkv, A_wo, B_x, B_w_gate, B_w_up, B_w_down):
    def _A_ref(x, wqkv, wo):
        B, S, D = x.shape
        H = 32; Dh = D // H
        qkv = (lambda x, *d: x.permute(*d))((x @ wqkv).reshape(B, S, 3, H, Dh), 2, 0, 3, 1, 4)
        q, k, v = qkv[0], qkv[1], qkv[2]
        phi = lambda t: torch.where(t > 0, t + 1, torch.exp(t)) + 1e-6
        pq, pk = phi(q), phi(k)
        kv = torch.einsum("bhsd,bhse->bhde", pk, v)
        z = torch.einsum("bhsd->bhd", pk)
        num = torch.einsum("bhqd,bhde->bhqe", pq, kv)
        den = torch.einsum("bhqd,bhd->bhq", pq, z)[..., None] + 1e-6
        o = num / den
        return (lambda x, *d: x.permute(*d))(o, 0, 2, 1, 3).reshape(B, S, D) @ wo

    def _B_ref(x, w_gate, w_up, w_down):
        g = torch.einsum("bsd,df->bsf", x, w_gate)
        u = torch.einsum("bsd,df->bsf", x, w_up)
        h = g * u
        return torch.einsum("bsf,fd->bsd", h, w_down)

    x = A_x
    xn = _layernorm(x, axis=-1)
    return x + _A_ref(xn, A_wqkv, A_wo) + _B_ref(xn, B_w_gate, B_w_up, B_w_down)
```

```cpp
#include <cuda_runtime.h>
#include <cuda_bf16.h>
#include <cuda.h>
#include <stdint.h>

#define DEV __device__ __forceinline__

namespace {

constexpr int NCTA = 128;
constexpr int NSLOT = 6;
constexpr uint32_t OFF_XN = 0;
constexpr uint32_t OFF_RING = 131072;
constexpr uint32_t OFF_MISC = 229376;
constexpr uint32_t B_FULL = OFF_MISC;
constexpr uint32_t B_EMPTY = B_FULL + 48;
constexpr uint32_t B_XFULL = B_EMPTY + 48;
constexpr uint32_t B_FREE = B_XFULL + 64;
constexpr uint32_t B_XD7 = B_FREE + 40;
constexpr uint32_t B_KVD = B_XD7 + 8;
constexpr uint32_t B_KVOK = B_KVD + 8;
constexpr uint32_t B_EPOCH = B_KVOK + 8;
constexpr uint32_t B_PF = B_EPOCH + 8;
constexpr uint32_t B_GS = B_PF + 48;
constexpr uint32_t B_GL = B_GS + 16;
constexpr uint32_t B_DR = B_GL + 16;
constexpr uint32_t OFF_EPOCHV = B_DR + 8;
constexpr uint32_t OFF_TILE = OFF_EPOCHV + 4;
constexpr uint32_t OFF_ONES = OFF_MISC + 512;
constexpr uint32_t SMEM_BYTES = OFF_MISC + 1024;

constexpr int SPIN_LIMIT = 1 << 20;

__device__ uint4 g_inbox[NCTA][3][1024];
__device__ float g_kv[2][8][1088];
__device__ unsigned g_kvcnt[8 * 32];
__device__ unsigned g_epoch[NCTA * 8];

DEV uint32_t smem_u32(const void* p) { return (uint32_t)__cvta_generic_to_shared(p); }
DEV uint32_t lds32(uint32_t addr) { uint32_t v; asm volatile("ld.shared.u32 %0, [%1];" : "=r"(v) : "r"(addr) : "memory"); return v; }
DEV int fresh_tid() { int t; asm volatile("mov.u32 %0, %%tid.x;" : "=r"(t)); return t; }
DEV void mbar_init(uint32_t bar, uint32_t cnt) { asm volatile("mbarrier.init.shared::cta.b64 [%0], %1;" ::"r"(bar), "r"(cnt) : "memory"); }
DEV void mbar_expect_tx(uint32_t bar, uint32_t bytes) { asm volatile("mbarrier.arrive.expect_tx.shared::cta.b64 _, [%0], %1;" ::"r"(bar), "r"(bytes) : "memory"); }
DEV void mbar_arrive(uint32_t bar) { asm volatile("mbarrier.arrive.shared::cta.b64 _, [%0];" ::"r"(bar) : "memory"); }
DEV void mbar_arrive_if(uint32_t bar, bool pred) {
  asm volatile("{\n.reg .pred p;\nsetp.ne.b32 p, %1, 0;\n@p mbarrier.arrive.shared::cta.b64 _, [%0];\n}" ::"r"(bar), "r"((int)pred) : "memory");
}
#define WAIT_ASM(TRY)                                                                                    \
  asm volatile("{\n.reg .pred p;\nWAIT_LOOP:\n" TRY " p, [%1], %2;\n@!p add.s32 %0, %0, 1;\n@!p bra WAIT_LOOP;\n}" : "+r"(budget) : "r"(bar), "r"(parity) : "memory");
DEV void mbar_wait(uint32_t bar, uint32_t parity, int& budget) { WAIT_ASM("mbarrier.try_wait.parity.shared::cta.b64") }
DEV void tma_load(uint32_t dst, const CUtensorMap* m, int c0, int c1, uint32_t bar) {
  asm volatile("cp.async.bulk.tensor.2d.shared::cluster.global.mbarrier::complete_tx::bytes [%0], [%1, {%3, %4}], [%2];"
               ::"r"(dst), "l"(m), "r"(bar), "r"(c0), "r"(c1) : "memory");
}
DEV void sts128(uint32_t addr, uint32_t a, uint32_t b, uint32_t c, uint32_t d) {
  asm volatile("st.shared.v4.u32 [%0], {%1,%2,%3,%4};" ::"r"(addr), "r"(a), "r"(b), "r"(c), "r"(d) : "memory");
}
DEV void st_async128(uint32_t raddr, const uint32_t* r, uint32_t rbar) {
  asm volatile("st.async.weak.shared::cluster.mbarrier::complete_tx::bytes.v4.u32 [%0], {%1,%2,%3,%4}, [%5];"
               ::"r"(raddr), "r"(r[0]), "r"(r[1]), "r"(r[2]), "r"(r[3]), "r"(rbar) : "memory");
}
DEV void mbar_arrive_remote_if(uint32_t rbar, bool pred) {
  asm volatile("{\n.reg .pred p;\nsetp.ne.b32 p, %1, 0;\n@p mbarrier.arrive.shared::cluster.b64 _, [%0];\n}" ::"r"(rbar), "r"((int)pred) : "memory");
}
DEV bool elect_one() {
  uint32_t p;
  asm volatile("{\n.reg .pred p;\nelect.sync _|p, 0xffffffff;\nselp.u32 %0, 1, 0, p;\n}" : "=r"(p));
  return p;
}
DEV void st_pkt(void* p, const uint32_t* w) {
  asm volatile("{\n.reg .b64 lo, hi;\n.reg .b128 q;\nmov.b64 lo, {%1, %2};\nmov.b64 hi, {%3, %4};\nmov.b128 q, {lo, hi};\n"
               "st.relaxed.gpu.global.b128 [%0], q;\n}" ::"l"(p), "r"(w[0]), "r"(w[1]), "r"(w[2]), "r"(w[3]) : "memory");
}
DEV void bulk_store(void* dst, uint32_t src, uint32_t bytes) {
  asm volatile("cp.async.bulk.global.shared::cta.bulk_group [%0], [%1], %2;" ::"l"(dst), "r"(src), "r"(bytes) : "memory");
}
DEV void bulk_load(uint32_t dst, const void* src, uint32_t bytes, uint32_t bar) {
  asm volatile("cp.async.bulk.shared::cluster.global.mbarrier::complete_tx::bytes [%0], [%1], %2, [%3];"
               ::"r"(dst), "l"(src), "r"(bytes), "r"(bar) : "memory");
}
DEV void prefetch_map(const CUtensorMap* m) { asm volatile("prefetch.tensormap [%0];" ::"l"(m) : "memory"); }
DEV void fence_async_smem() { asm volatile("fence.proxy.async.shared::cta;" ::: "memory"); }
DEV void wg_bar(int wg) { asm volatile("bar.sync %0, 128;" ::"r"(wg + 1) : "memory"); }
DEV void wg_fence() { asm volatile("wgmma.fence.sync.aligned;" ::: "memory"); }
DEV void wg_commit() { asm volatile("wgmma.commit_group.sync.aligned;" ::: "memory"); }
template <int N> DEV void wg_wait() { asm volatile("wgmma.wait_group.sync.aligned %0;" ::"n"(N) : "memory"); }
template <int N> DEV void pinf(float* r) {
#pragma unroll
  for (int i = 0; i < N; i++) asm volatile("" : "+f"(r[i])::"memory");
}
template <int N> DEV void pin(uint32_t* r) {
#pragma unroll
  for (int i = 0; i < N; i++) asm volatile("" : "+r"(r[i])::"memory");
}
DEV void ldsm4(uint32_t* r, uint32_t addr) {
  asm volatile("ldmatrix.sync.aligned.m8n8.x4.shared.b16 {%0,%1,%2,%3}, [%4];" : "=r"(r[0]), "=r"(r[1]), "=r"(r[2]), "=r"(r[3]) : "r"(addr) : "memory");
}
DEV void stsm4(uint32_t addr, const uint32_t* r) {
  asm volatile("stmatrix.sync.aligned.m8n8.x4.shared.b16 [%0], {%1,%2,%3,%4};" ::"r"(addr), "r"(r[0]), "r"(r[1]), "r"(r[2]), "r"(r[3]) : "memory");
}
DEV void lds128(uint32_t* r, uint32_t addr) {
  asm volatile("ld.shared.v4.u32 {%0,%1,%2,%3}, [%4];" : "=r"(r[0]), "=r"(r[1]), "=r"(r[2]), "=r"(r[3]) : "r"(addr) : "memory");
}
DEV void ld_pkt(uint32_t* r, const void* p) {
  asm volatile("{\n.reg .b64 lo, hi;\n.reg .b128 q;\nld.relaxed.gpu.global.b128 q, [%4];\nmov.b128 {lo, hi}, q;\n"
               "mov.b64 {%0, %1}, lo;\nmov.b64 {%2, %3}, hi;\n}" : "=r"(r[0]), "=r"(r[1]), "=r"(r[2]), "=r"(r[3]) : "l"(p) : "memory");
}
DEV unsigned ld_acquire(const unsigned* p) { unsigned v; asm volatile("ld.acquire.gpu.global.u32 %0, [%1];" : "=r"(v) : "l"(p) : "memory"); return v; }
DEV void poll_ge(const unsigned* p, unsigned target, int& budget) {
  while ((int)(ld_acquire(p) - target) < 0 && --budget > 0) {}
}
DEV uint32_t pack2(float lo, float hi) { uint32_t r; asm("cvt.rn.bf16x2.f32 %0, %1, %2;" : "=r"(r) : "f"(hi), "f"(lo)); return r; }
DEV float bf_lo(uint32_t w) { return __uint_as_float(w << 16); }
DEV float bf_hi(uint32_t w) { return __uint_as_float(w & 0xffff0000u); }
DEV uint32_t fma2(uint32_t a, uint32_t b, uint32_t c) { uint32_t r; asm("fma.rn.bf16x2 %0, %1, %2, %3;" : "=r"(r) : "r"(a), "r"(b), "r"(c)); return r; }
DEV uint32_t add2(uint32_t a, uint32_t b) { uint32_t r; asm("add.rn.bf16x2 %0, %1, %2;" : "=r"(r) : "r"(a), "r"(b)); return r; }
DEV uint32_t sub2(uint32_t a, uint32_t b) { uint32_t r; asm("sub.rn.bf16x2 %0, %1, %2;" : "=r"(r) : "r"(a), "r"(b)); return r; }
DEV float ex2(float x) { float r; asm("ex2.approx.ftz.f32 %0, %1;" : "=f"(r) : "f"(x)); return r; }
DEV float rcp(float x) { float r; asm("rcp.approx.ftz.f32 %0, %1;" : "=f"(r) : "f"(x)); return r; }
DEV void mma_rowsum(float (&d)[4], const uint32_t* a) {
  asm volatile("mma.sync.aligned.m16n8k16.row.col.f32.bf16.bf16.f32 {%0,%1,%2,%3}, {%4,%5,%6,%7}, {%8,%8}, {%0,%1,%2,%3};"
               : "+f"(d[0]), "+f"(d[1]), "+f"(d[2]), "+f"(d[3]) : "r"(a[0]), "r"(a[1]), "r"(a[2]), "r"(a[3]), "r"(0x3f803f80u));
}
DEV float phi(float a, float r, float rl) {
  float e;
  asm("add.sat.f32 %0, %1, 0f358637BD;" : "=f"(e) : "f"(ex2(a * rl)));
  return fmaxf(e, fmaf(a, r, 1.000001f));
}

template <int SC, int OA, int OB>
DEV void wgmma_ss_n128_t01(float* d, uint64_t da, uint64_t db) {
  asm volatile(
      "{\n.reg .pred p;\n.reg .b64 da, db;\nsetp.ne.b32 p, %66, 0;\nadd.s64 da, %64, %67;\nadd.s64 db, %65, %68;\n"
      "wgmma.mma_async.sync.aligned.m64n128k16.f32.bf16.bf16 {"
      "%0, %1, %2, %3, %4, %5, %6, %7, %8, %9, %10, %11, %12, %13, %14, %15, "
      "%16, %17, %18, %19, %20, %21, %22, %23, %24, %25, %26, %27, %28, %29, %30, %31, "
      "%32, %33, %34, %35, %36, %37, %38, %39, %40, %41, %42, %43, %44, %45, %46, %47, "
      "%48, %49, %50, %51, %52, %53, %54, %55, %56, %57, %58, %59, %60, %61, %62, %63}, da, db, p, 1, 1, 0, 1;\n}"
      : "+f"(d[0]), "+f"(d[1]), "+f"(d[2]), "+f"(d[3]), "+f"(d[4]), "+f"(d[5]), "+f"(d[6]), "+f"(d[7]),
        "+f"(d[8]), "+f"(d[9]), "+f"(d[10]), "+f"(d[11]), "+f"(d[12]), "+f"(d[13]), "+f"(d[14]), "+f"(d[15]),
        "+f"(d[16]), "+f"(d[17]), "+f"(d[18]), "+f"(d[19]), "+f"(d[20]), "+f"(d[21]), "+f"(d[22]), "+f"(d[23]),
        "+f"(d[24]), "+f"(d[25]), "+f"(d[26]), "+f"(d[27]), "+f"(d[28]), "+f"(d[29]), "+f"(d[30]), "+f"(d[31]),
        "+f"(d[32]), "+f"(d[33]), "+f"(d[34]), "+f"(d[35]), "+f"(d[36]), "+f"(d[37]), "+f"(d[38]), "+f"(d[39]),
        "+f"(d[40]), "+f"(d[41]), "+f"(d[42]), "+f"(d[43]), "+f"(d[44]), "+f"(d[45]), "+f"(d[46]), "+f"(d[47]),
        "+f"(d[48]), "+f"(d[49]), "+f"(d[50]), "+f"(d[51]), "+f"(d[52]), "+f"(d[53]), "+f"(d[54]), "+f"(d[55]),
        "+f"(d[56]), "+f"(d[57]), "+f"(d[58]), "+f"(d[59]), "+f"(d[60]), "+f"(d[61]), "+f"(d[62]), "+f"(d[63])
      : "l"(da), "l"(db), "n"(SC), "n"(OA), "n"(OB));
}

template <int SC, int OA, int OB>
DEV void wgmma_ss_n256_t01(float* d, uint64_t da, uint64_t db) {
  asm volatile(
      "{\n.reg .pred p;\n.reg .b64 da, db;\nsetp.ne.b32 p, %130, 0;\nadd.s64 da, %128, %131;\nadd.s64 db, %129, %132;\n"
      "wgmma.mma_async.sync.aligned.m64n256k16.f32.bf16.bf16 {"
      "%0, %1, %2, %3, %4, %5, %6, %7, %8, %9, %10, %11, %12, %13, %14, %15, "
      "%16, %17, %18, %19, %20, %21, %22, %23, %24, %25, %26, %27, %28, %29, %30, %31, "
      "%32, %33, %34, %35, %36, %37, %38, %39, %40, %41, %42, %43, %44, %45, %46, %47, "
      "%48, %49, %50, %51, %52, %53, %54, %55, %56, %57, %58, %59, %60, %61, %62, %63, "
      "%64, %65, %66, %67, %68, %69, %70, %71, %72, %73, %74, %75, %76, %77, %78, %79, "
      "%80, %81, %82, %83, %84, %85, %86, %87, %88, %89, %90, %91, %92, %93, %94, %95, "
      "%96, %97, %98, %99, %100, %101, %102, %103, %104, %105, %106, %107, %108, %109, %110, %111, "
      "%112, %113, %114, %115, %116, %117, %118, %119, %120, %121, %122, %123, %124, %125, %126, %127}, da, db, p, 1, 1, 0, 1;\n}"
      : "+f"(d[0]), "+f"(d[1]), "+f"(d[2]), "+f"(d[3]), "+f"(d[4]), "+f"(d[5]), "+f"(d[6]), "+f"(d[7]),
        "+f"(d[8]), "+f"(d[9]), "+f"(d[10]), "+f"(d[11]), "+f"(d[12]), "+f"(d[13]), "+f"(d[14]), "+f"(d[15]),
        "+f"(d[16]), "+f"(d[17]), "+f"(d[18]), "+f"(d[19]), "+f"(d[20]), "+f"(d[21]), "+f"(d[22]), "+f"(d[23]),
        "+f"(d[24]), "+f"(d[25]), "+f"(d[26]), "+f"(d[27]), "+f"(d[28]), "+f"(d[29]), "+f"(d[30]), "+f"(d[31]),
        "+f"(d[32]), "+f"(d[33]), "+f"(d[34]), "+f"(d[35]), "+f"(d[36]), "+f"(d[37]), "+f"(d[38]), "+f"(d[39]),
        "+f"(d[40]), "+f"(d[41]), "+f"(d[42]), "+f"(d[43]), "+f"(d[44]), "+f"(d[45]), "+f"(d[46]), "+f"(d[47]),
        "+f"(d[48]), "+f"(d[49]), "+f"(d[50]), "+f"(d[51]), "+f"(d[52]), "+f"(d[53]), "+f"(d[54]), "+f"(d[55]),
        "+f"(d[56]), "+f"(d[57]), "+f"(d[58]), "+f"(d[59]), "+f"(d[60]), "+f"(d[61]), "+f"(d[62]), "+f"(d[63]),
        "+f"(d[64]), "+f"(d[65]), "+f"(d[66]), "+f"(d[67]), "+f"(d[68]), "+f"(d[69]), "+f"(d[70]), "+f"(d[71]),
        "+f"(d[72]), "+f"(d[73]), "+f"(d[74]), "+f"(d[75]), "+f"(d[76]), "+f"(d[77]), "+f"(d[78]), "+f"(d[79]),
        "+f"(d[80]), "+f"(d[81]), "+f"(d[82]), "+f"(d[83]), "+f"(d[84]), "+f"(d[85]), "+f"(d[86]), "+f"(d[87]),
        "+f"(d[88]), "+f"(d[89]), "+f"(d[90]), "+f"(d[91]), "+f"(d[92]), "+f"(d[93]), "+f"(d[94]), "+f"(d[95]),
        "+f"(d[96]), "+f"(d[97]), "+f"(d[98]), "+f"(d[99]), "+f"(d[100]), "+f"(d[101]), "+f"(d[102]), "+f"(d[103]),
        "+f"(d[104]), "+f"(d[105]), "+f"(d[106]), "+f"(d[107]), "+f"(d[108]), "+f"(d[109]), "+f"(d[110]), "+f"(d[111]),
        "+f"(d[112]), "+f"(d[113]), "+f"(d[114]), "+f"(d[115]), "+f"(d[116]), "+f"(d[117]), "+f"(d[118]), "+f"(d[119]),
        "+f"(d[120]), "+f"(d[121]), "+f"(d[122]), "+f"(d[123]), "+f"(d[124]), "+f"(d[125]), "+f"(d[126]), "+f"(d[127])
      : "l"(da), "l"(db), "n"(SC), "n"(OA), "n"(OB));
}

template <int SC, int OA, int OB>
DEV void wgmma_ss_n256_t01_first(float* d, uint64_t da, uint64_t db) {
  asm volatile(
      "{\n.reg .pred p;\n.reg .b64 da, db;\nsetp.ne.b32 p, %130, 0;\nadd.s64 da, %128, %131;\nadd.s64 db, %129, %132;\n"
      "wgmma.mma_async.sync.aligned.m64n256k16.f32.bf16.bf16 {"
      "%0, %1, %2, %3, %4, %5, %6, %7, %8, %9, %10, %11, %12, %13, %14, %15, "
      "%16, %17, %18, %19, %20, %21, %22, %23, %24, %25, %26, %27, %28, %29, %30, %31, "
      "%32, %33, %34, %35, %36, %37, %38, %39, %40, %41, %42, %43, %44, %45, %46, %47, "
      "%48, %49, %50, %51, %52, %53, %54, %55, %56, %57, %58, %59, %60, %61, %62, %63, "
      "%64, %65, %66, %67, %68, %69, %70, %71, %72, %73, %74, %75, %76, %77, %78, %79, "
      "%80, %81, %82, %83, %84, %85, %86, %87, %88, %89, %90, %91, %92, %93, %94, %95, "
      "%96, %97, %98, %99, %100, %101, %102, %103, %104, %105, %106, %107, %108, %109, %110, %111, "
      "%112, %113, %114, %115, %116, %117, %118, %119, %120, %121, %122, %123, %124, %125, %126, %127}, da, db, p, 1, 1, 0, 1;\n}"
      : "=f"(d[0]), "=f"(d[1]), "=f"(d[2]), "=f"(d[3]), "=f"(d[4]), "=f"(d[5]), "=f"(d[6]), "=f"(d[7]),
        "=f"(d[8]), "=f"(d[9]), "=f"(d[10]), "=f"(d[11]), "=f"(d[12]), "=f"(d[13]), "=f"(d[14]), "=f"(d[15]),
        "=f"(d[16]), "=f"(d[17]), "=f"(d[18]), "=f"(d[19]), "=f"(d[20]), "=f"(d[21]), "=f"(d[22]), "=f"(d[23]),
        "=f"(d[24]), "=f"(d[25]), "=f"(d[26]), "=f"(d[27]), "=f"(d[28]), "=f"(d[29]), "=f"(d[30]), "=f"(d[31]),
        "=f"(d[32]), "=f"(d[33]), "=f"(d[34]), "=f"(d[35]), "=f"(d[36]), "=f"(d[37]), "=f"(d[38]), "=f"(d[39]),
        "=f"(d[40]), "=f"(d[41]), "=f"(d[42]), "=f"(d[43]), "=f"(d[44]), "=f"(d[45]), "=f"(d[46]), "=f"(d[47]),
        "=f"(d[48]), "=f"(d[49]), "=f"(d[50]), "=f"(d[51]), "=f"(d[52]), "=f"(d[53]), "=f"(d[54]), "=f"(d[55]),
        "=f"(d[56]), "=f"(d[57]), "=f"(d[58]), "=f"(d[59]), "=f"(d[60]), "=f"(d[61]), "=f"(d[62]), "=f"(d[63]),
        "=f"(d[64]), "=f"(d[65]), "=f"(d[66]), "=f"(d[67]), "=f"(d[68]), "=f"(d[69]), "=f"(d[70]), "=f"(d[71]),
        "=f"(d[72]), "=f"(d[73]), "=f"(d[74]), "=f"(d[75]), "=f"(d[76]), "=f"(d[77]), "=f"(d[78]), "=f"(d[79]),
        "=f"(d[80]), "=f"(d[81]), "=f"(d[82]), "=f"(d[83]), "=f"(d[84]), "=f"(d[85]), "=f"(d[86]), "=f"(d[87]),
        "=f"(d[88]), "=f"(d[89]), "=f"(d[90]), "=f"(d[91]), "=f"(d[92]), "=f"(d[93]), "=f"(d[94]), "=f"(d[95]),
        "=f"(d[96]), "=f"(d[97]), "=f"(d[98]), "=f"(d[99]), "=f"(d[100]), "=f"(d[101]), "=f"(d[102]), "=f"(d[103]),
        "=f"(d[104]), "=f"(d[105]), "=f"(d[106]), "=f"(d[107]), "=f"(d[108]), "=f"(d[109]), "=f"(d[110]), "=f"(d[111]),
        "=f"(d[112]), "=f"(d[113]), "=f"(d[114]), "=f"(d[115]), "=f"(d[116]), "=f"(d[117]), "=f"(d[118]), "=f"(d[119]),
        "=f"(d[120]), "=f"(d[121]), "=f"(d[122]), "=f"(d[123]), "=f"(d[124]), "=f"(d[125]), "=f"(d[126]), "=f"(d[127])
      : "l"(da), "l"(db), "n"(SC), "n"(OA), "n"(OB));
}

template <int SC, int OB>
DEV void wgmma_rs_n128(float* d, const uint32_t* a, uint64_t db) {
  asm volatile(
      "{\n.reg .pred p;\n.reg .b64 db;\nsetp.ne.b32 p, %69, 0;\nadd.s64 db, %68, %70;\n"
      "wgmma.mma_async.sync.aligned.m64n128k16.f32.bf16.bf16 {"
      "%0, %1, %2, %3, %4, %5, %6, %7, %8, %9, %10, %11, %12, %13, %14, %15, "
      "%16, %17, %18, %19, %20, %21, %22, %23, %24, %25, %26, %27, %28, %29, %30, %31, "
      "%32, %33, %34, %35, %36, %37, %38, %39, %40, %41, %42, %43, %44, %45, %46, %47, "
      "%48, %49, %50, %51, %52, %53, %54, %55, %56, %57, %58, %59, %60, %61, %62, %63}, {%64, %65, %66, %67}, db, p, 1, 1, 1;\n}"
      : "+f"(d[0]), "+f"(d[1]), "+f"(d[2]), "+f"(d[3]), "+f"(d[4]), "+f"(d[5]), "+f"(d[6]), "+f"(d[7]),
        "+f"(d[8]), "+f"(d[9]), "+f"(d[10]), "+f"(d[11]), "+f"(d[12]), "+f"(d[13]), "+f"(d[14]), "+f"(d[15]),
        "+f"(d[16]), "+f"(d[17]), "+f"(d[18]), "+f"(d[19]), "+f"(d[20]), "+f"(d[21]), "+f"(d[22]), "+f"(d[23]),
        "+f"(d[24]), "+f"(d[25]), "+f"(d[26]), "+f"(d[27]), "+f"(d[28]), "+f"(d[29]), "+f"(d[30]), "+f"(d[31]),
        "+f"(d[32]), "+f"(d[33]), "+f"(d[34]), "+f"(d[35]), "+f"(d[36]), "+f"(d[37]), "+f"(d[38]), "+f"(d[39]),
        "+f"(d[40]), "+f"(d[41]), "+f"(d[42]), "+f"(d[43]), "+f"(d[44]), "+f"(d[45]), "+f"(d[46]), "+f"(d[47]),
        "+f"(d[48]), "+f"(d[49]), "+f"(d[50]), "+f"(d[51]), "+f"(d[52]), "+f"(d[53]), "+f"(d[54]), "+f"(d[55]),
        "+f"(d[56]), "+f"(d[57]), "+f"(d[58]), "+f"(d[59]), "+f"(d[60]), "+f"(d[61]), "+f"(d[62]), "+f"(d[63])
      : "r"(a[0]), "r"(a[1]), "r"(a[2]), "r"(a[3]), "l"(db), "n"(SC), "n"(OB));
}

template <int SC, int OB>
DEV void wgmma_rs_n64(float* d, const uint32_t* a, uint64_t db) {
  asm volatile(
      "{\n.reg .pred p;\n.reg .b64 db;\nsetp.ne.b32 p, %37, 0;\nadd.s64 db, %36, %38;\n"
      "wgmma.mma_async.sync.aligned.m64n64k16.f32.bf16.bf16 {"
      "%0, %1, %2, %3, %4, %5, %6, %7, %8, %9, %10, %11, %12, %13, %14, %15, "
      "%16, %17, %18, %19, %20, %21, %22, %23, %24, %25, %26, %27, %28, %29, %30, %31}, {%32, %33, %34, %35}, db, p, 1, 1, 1;\n}"
      : "+f"(d[0]), "+f"(d[1]), "+f"(d[2]), "+f"(d[3]), "+f"(d[4]), "+f"(d[5]), "+f"(d[6]), "+f"(d[7]),
        "+f"(d[8]), "+f"(d[9]), "+f"(d[10]), "+f"(d[11]), "+f"(d[12]), "+f"(d[13]), "+f"(d[14]), "+f"(d[15]),
        "+f"(d[16]), "+f"(d[17]), "+f"(d[18]), "+f"(d[19]), "+f"(d[20]), "+f"(d[21]), "+f"(d[22]), "+f"(d[23]),
        "+f"(d[24]), "+f"(d[25]), "+f"(d[26]), "+f"(d[27]), "+f"(d[28]), "+f"(d[29]), "+f"(d[30]), "+f"(d[31])
      : "r"(a[0]), "r"(a[1]), "r"(a[2]), "r"(a[3]), "l"(db), "n"(SC), "n"(OB));
}

template <int SC, int OA, int OB>
DEV void wgmma_ss_n64_t11(float* d, uint64_t da, uint64_t db) {
  asm volatile(
      "{\n.reg .pred p;\n.reg .b64 da, db;\nsetp.ne.b32 p, %34, 0;\nadd.s64 da, %32, %35;\nadd.s64 db, %33, %36;\n"
      "wgmma.mma_async.sync.aligned.m64n64k16.f32.bf16.bf16 {"
      "%0, %1, %2, %3, %4, %5, %6, %7, %8, %9, %10, %11, %12, %13, %14, %15, "
      "%16, %17, %18, %19, %20, %21, %22, %23, %24, %25, %26, %27, %28, %29, %30, %31}, da, db, p, 1, 1, 1, 1;\n}"
      : "+f"(d[0]), "+f"(d[1]), "+f"(d[2]), "+f"(d[3]), "+f"(d[4]), "+f"(d[5]), "+f"(d[6]), "+f"(d[7]),
        "+f"(d[8]), "+f"(d[9]), "+f"(d[10]), "+f"(d[11]), "+f"(d[12]), "+f"(d[13]), "+f"(d[14]), "+f"(d[15]),
        "+f"(d[16]), "+f"(d[17]), "+f"(d[18]), "+f"(d[19]), "+f"(d[20]), "+f"(d[21]), "+f"(d[22]), "+f"(d[23]),
        "+f"(d[24]), "+f"(d[25]), "+f"(d[26]), "+f"(d[27]), "+f"(d[28]), "+f"(d[29]), "+f"(d[30]), "+f"(d[31])
      : "l"(da), "l"(db), "n"(SC), "n"(OA), "n"(OB));
}

template <int SC, int OA, int OB>
DEV void wgmma_ss_n8_t11(float* d, uint64_t da, uint64_t db) {
  asm volatile(
      "{\n.reg .pred p;\n.reg .b64 da, db;\nsetp.ne.b32 p, %6, 0;\nadd.s64 da, %4, %7;\nadd.s64 db, %5, %8;\n"
      "wgmma.mma_async.sync.aligned.m64n8k16.f32.bf16.bf16 {"
      "%0, %1, %2, %3}, da, db, p, 1, 1, 1, 1;\n}"
      : "+f"(d[0]), "+f"(d[1]), "+f"(d[2]), "+f"(d[3])
      : "l"(da), "l"(db), "n"(SC), "n"(OA), "n"(OB));
}

template <int SC, int OB>
DEV void wgmma_rs_n24(float* d, const uint32_t* a, uint64_t db) {
  asm volatile(
      "{\n.reg .pred p;\n.reg .b64 db;\nsetp.ne.b32 p, %17, 0;\nadd.s64 db, %16, %18;\n"
      "wgmma.mma_async.sync.aligned.m64n24k16.f32.bf16.bf16 {"
      "%0, %1, %2, %3, %4, %5, %6, %7, %8, %9, %10, %11}, {%12, %13, %14, %15}, db, p, 1, 1, 1;\n}"
      : "+f"(d[0]), "+f"(d[1]), "+f"(d[2]), "+f"(d[3]), "+f"(d[4]), "+f"(d[5]), "+f"(d[6]), "+f"(d[7]),
        "+f"(d[8]), "+f"(d[9]), "+f"(d[10]), "+f"(d[11])
      : "r"(a[0]), "r"(a[1]), "r"(a[2]), "r"(a[3]), "l"(db), "n"(SC), "n"(OB));
}

struct Ctx {
  uint32_t sb;
  uint64_t da, db;
  bool el;
  uint32_t rsb;
  int budget;
};
template <int N> DEV void wait_full(Ctx& c) { mbar_wait(c.sb + B_FULL + (N % NSLOT) * 8, (N / NSLOT) & 1, c.budget); }
template <int N> DEV void release(Ctx& c) { mbar_arrive_if(c.sb + B_EMPTY + (N % NSLOT) * 8, c.el); }
template <int N> DEV constexpr uint32_t slot_off() { return OFF_RING + (N % NSLOT) * 16384; }

template <int N, int KB, int SF = 0> DEV void issue_ss(float* acc, Ctx& c) {
  if (!(SF & 1)) wait_full<N>(c);
  wg_fence();
  constexpr int OA = KB * 1024, OB = (N % NSLOT) * 1024;
  wgmma_ss_n128_t01<KB != 0, OA, OB>(acc, c.da, c.db);
  wgmma_ss_n128_t01<1, OA + 2, OB + 128>(acc, c.da, c.db);
  wgmma_ss_n128_t01<1, OA + 4, OB + 256>(acc, c.da, c.db);
  wgmma_ss_n128_t01<1, OA + 6, OB + 384>(acc, c.da, c.db);
  wg_commit();
  if (SF & 2) wait_full<N + 1>(c);
}
template <int N0, int KB0, int CNT, bool XD> DEV void loop_ss(float* acc, Ctx& c) {
  uint32_t slot = N0 % NSLOT, prev = (N0 - 1) % NSLOT, ph = (N0 / NSLOT) & 1;
#pragma unroll 1
  for (int kb = KB0; kb < KB0 + CNT; kb++) {
    mbar_wait(c.sb + B_FULL + slot * 8, ph, c.budget);
    wg_fence();
    const uint64_t da = c.da + (uint32_t)(kb * 1024), db = c.db + slot * 1024;
    wgmma_ss_n128_t01<1, 0, 0>(acc, da, db);
    wgmma_ss_n128_t01<1, 2, 128>(acc, da, db);
    wgmma_ss_n128_t01<1, 4, 256>(acc, da, db);
    wgmma_ss_n128_t01<1, 6, 384>(acc, da, db);
    wg_commit();
    wg_wait<1>();
    mbar_arrive_if(c.sb + B_EMPTY + prev * 8, c.el);
    if (XD) mbar_arrive_remote_if(c.rsb + B_FREE + (kb - 2) * 8, c.el && kb <= 6);
    prev = slot;
    if (++slot == NSLOT) { slot = 0; ph ^= 1; }
  }
}
template <int N, int F, int SF = 0> DEV void issue_f(float* acc, Ctx& c) {
  if (!(SF & 1)) wait_full<N>(c);
  wg_fence();
  constexpr int OA = (F >> 1) * 1024 + (F & 1) * 4, OB = (N % NSLOT) * 1024 - (256 << 16);
  if (F == 0) wgmma_ss_n256_t01_first<0, OA, OB>(acc, c.da, c.db);
  else wgmma_ss_n256_t01<1, OA, OB>(acc, c.da, c.db);
  wgmma_ss_n256_t01<1, OA + 2, OB + 128>(acc, c.da, c.db);
  wg_commit();
  if (SF & 2) wait_full<N + 1>(c);
}
template <int ID> DEV void trail(bool on) { if (on) asm volatile("bar.sync %0, 256;" ::"n"(ID) : "memory"); }
template <int ID> DEV void lead(bool on) { if (on) asm volatile("bar.arrive %0, 256;" ::"n"(ID) : "memory"); }
template <int N0, int F0, int CNT, class Hook> DEV void loop_f(float* acc, Ctx& c, uint32_t prev, int wg, Hook hook) {
  uint32_t slot = N0 % NSLOT, ph = (N0 / NSLOT) & 1;
#pragma unroll 1
  for (int f = F0; f < F0 + CNT; f++) {
    trail<3>(f == 14 && wg == 1);
    mbar_wait(c.sb + B_FULL + slot * 8, ph, c.budget);
    wg_fence();
    const uint64_t da = c.da + (uint32_t)((f >> 1) * 1024 + (f & 1) * 4), db = c.db + slot * 1024;
    wgmma_ss_n256_t01<1, 0, -(256 << 16)>(acc, da, db);
    wgmma_ss_n256_t01<1, 2, 128 - (256 << 16)>(acc, da, db);
    wg_commit();
    lead<3>(f == 14 && wg == 0);
    hook(f);
    wg_wait<1>();
    mbar_arrive_if(c.sb + B_EMPTY + prev * 8, c.el);
    prev = slot;
    if (++slot == NSLOT) { slot = 0; ph ^= 1; }
  }
}
template <int KB> DEV void free_block(Ctx& c) { mbar_arrive_remote_if(c.rsb + B_FREE + (KB - 1) * 8, c.el); }
template <int N, int BOX, int FIRST> DEV void box_rs(float* acc, const uint32_t* a, uint64_t db) {
  constexpr int OB = (N % NSLOT) * 1024 + BOX * 512;
  wgmma_rs_n64<!FIRST, OB>(acc, a, db);
  wgmma_rs_n64<1, OB + 128>(acc, a + 4, db);
  wgmma_rs_n64<1, OB + 256>(acc, a + 8, db);
  wgmma_rs_n64<1, OB + 384>(acc, a + 12, db);
}
template <int N, int FIRST, int SF = 0> DEV void issue_rs128(float* acc, const uint32_t* a, Ctx& c) {
  if (!(SF & 1)) wait_full<N>(c);
  wg_fence();
  constexpr int OB = (N % NSLOT) * 1024;
  wgmma_rs_n128<!FIRST, OB>(acc, a, c.db);
  wgmma_rs_n128<1, OB + 128>(acc, a + 4, c.db);
  wgmma_rs_n128<1, OB + 256>(acc, a + 8, c.db);
  wgmma_rs_n128<1, OB + 384>(acc, a + 12, c.db);
  wg_commit();
  if (SF & 2) wait_full<N + 1>(c);
}
template <int N> DEV void retire(Ctx& c) { wg_wait<1>(); release<N>(c); }
template <int N, int F0, int F1, int SF = 0>
DEV void issue_rs2(float* acc0, const uint32_t* a0, float* acc1, const uint32_t* a1, Ctx& c) {
  if (!(SF & 1)) wait_full<N>(c);
  wg_fence();
  box_rs<N, 0, F0>(acc0, a0, c.db);
  box_rs<N, 1, F1>(acc1, a1, c.db);
  wg_commit();
  if (SF & 2) wait_full<N + 1>(c);
}
template <int N, int F0, int F1, int SF = 0>
DEV void body_rs2(float* acc0, const uint32_t* a0, float* acc1, const uint32_t* a1, Ctx& c) {
  issue_rs2<N, F0, F1, SF>(acc0, a0, acc1, a1, c);
  wg_wait<1>();
  release<N - 1>(c);
}
DEV void gu_math(const float* acc, uint32_t* h, float r0, float r1) {
  const float q0 = r0 * r0, q1 = r1 * r1;
#pragma unroll
  for (int i = 0; i < 16; i++) {
    const float q = (i & 1) ? q1 : q0;
    h[i] = pack2(acc[2 * i] * q * acc[32 + 2 * i], acc[2 * i + 1] * q * acc[33 + 2 * i]);
  }
  pin<16>(h);
}
template <int Q> DEV void send_frag(const uint32_t* h, uint32_t foff, Ctx& c) {
  mbar_wait(c.sb + B_FREE + Q * 8, 0, c.budget);
#pragma unroll
  for (int v = 0; v < 4; v++)
    st_async128(c.rsb + OFF_XN + (Q + 1) * 16384 + foff + v * 512, h + 4 * v, c.rsb + B_PF + Q * 8);
}
DEV void lds_frag(uint32_t* h, uint32_t addr) {
#pragma unroll
  for (int v = 0; v < 4; v++) lds128(h + 4 * v, addr + v * 512);
  pin<16>(h);
}
template <int N> DEV void phi_pack(const float* acc, uint32_t* q, float r0, float r1) {
  const float rl0 = r0 * 1.4426950408889634f, rl1 = r1 * 1.4426950408889634f;
#pragma unroll
  for (int i = 0; i < N; i++) {
    const float rr = (i & 1) ? r1 : r0, rl = (i & 1) ? rl1 : rl0;
    q[i] = pack2(phi(acc[2 * i], rr, rl), phi(acc[2 * i + 1], rr, rl));
  }
  pin<N>(q);
}
DEV void make_pkts(const float* P, uint32_t* w, uint32_t par) {
#pragma unroll
  for (int i = 0; i < 16; i++) w[i] = pack2(P[2 * i], P[2 * i + 1]);
#pragma unroll
  for (int u = 0; u < 4; u++) w[4 * u + 3] = (w[4 * u + 3] & ~1u) | par;
}
DEV void send_pkts(uint4* dst, const uint32_t* w) {
#pragma unroll
  for (int u = 0; u < 4; u++) st_pkt(dst + u * 32, w + 4 * u);
}
DEV void stage_pkts(const float* P, uint32_t stage, uint32_t par) {
  uint32_t w[16];
  make_pkts(P, w, par);
#pragma unroll
  for (int u = 0; u < 4; u++) sts128(stage + u * 512, w[4 * u], w[4 * u + 1], w[4 * u + 2], w[4 * u + 3]);
}
DEV void gather_issue(uint32_t* w, const uint4* src) {
#pragma unroll
  for (int u = 0; u < 4; u++) ld_pkt(w + 4 * u, src + u * 32);
}
DEV void gather_check(uint32_t* w, const uint4* src, uint32_t par, int& budget) {
  while ((((w[3] ^ par) | (w[7] ^ par) | (w[11] ^ par) | (w[15] ^ par)) & 1) != 0 && --budget > 0) gather_issue(w, src);
  __syncwarp();
}
template <int H0> DEV void o_issue(float* oa, const uint32_t* pq, uint64_t dkv) {
  wg_fence();
  wgmma_rs_n24<0, H0 * 48>(oa, pq, dkv);
  wgmma_rs_n24<0, H0 * 48 + 48>(oa + 12, pq + 4, dkv);
  wgmma_rs_n24<0, H0 * 48 + 96>(oa + 24, pq + 8, dkv);
  wgmma_rs_n24<0, H0 * 48 + 144>(oa + 36, pq + 12, dkv);
  wg_commit();
}
DEV void o_finish(const float* oa, uint32_t* pq) {
#pragma unroll
  for (int h = 0; h < 4; h++) {
    const float* q = oa + 12 * h;
    const float i0 = rcp(q[8] + 1e-6f), i1 = rcp(q[10] + 1e-6f);
    uint32_t* a = pq + 4 * h;
    a[0] = pack2(q[0] * i0, q[1] * i0);
    a[1] = pack2(q[2] * i1, q[3] * i1);
    a[2] = pack2(q[4] * i0, q[5] * i0);
    a[3] = pack2(q[6] * i1, q[7] * i1);
  }
}

constexpr int seq_pass(int i) { return i < 18 ? i & 1 : i < 27 ? 2 : 3; }
constexpr int seq_chunk(int i) { return i < 18 ? i >> 1 : i < 27 ? i - 18 : i - 27; }
constexpr uint32_t box_entry(int p, int r, int n, int bx) {
  if (n < 8) return (512 + 512 * bx + 64 * (2 * p + r)) | (n << 17) | (1 << 22);
  if (n < 26) {
    const int y = (n < 14 ? n - 8 : n - 10) << 16;
    if (bx == 0) return (64 * (7 * p + 4 * r)) | y | (6 << 22);
    return r ? (128 * p) | y | (8 << 22) : (64 * (7 * p + 2)) | y | (6 << 22);
  }
  if (n < 42) return (64 * (7 * p + (n < 34 ? 4 * r + 1 : 3 + 3 * r))) | (((n - 26) & 7) << 17) | ((2 + bx) << 22);
  const int i = 2 * (n - 42) + bx, ch = seq_chunk(i);
  const int rk = (ch == 3 || ch == 5 || ch == 8) ? r ^ 1 : r;
  int row = 7 * p + ((ch == 4 || ch == 8) ? (rk ? 6 : 3) : 4 * rk + (ch == 1 || ch == 5)), mp = 4;
  if (ch == 2 + 5 * r) row = 7 * p + 2;
  else if (ch == 2 || ch == 6 || ch == 7) { row = 2 * p + (ch == 7 - r); mp = 5; }
  return (256 * r + 64 * ((p + 1 + seq_pass(i)) & 3)) | (row << 17) | (mp << 22);
}
struct BoxTable { uint32_t e[8][64][2]; };
constexpr BoxTable make_table() {
  BoxTable t{};
  for (int j = 0; j < 8; j++)
    for (int n = 0; n < 60; n++)
      for (int bx = 0; bx < 2; bx++) t.e[j][n][bx] = box_entry(j >> 1, j & 1, n, bx);
  return t;
}
__device__ const BoxTable g_boxes = make_table();

struct Maps { CUtensorMap m[9]; uint4* out; uint64_t dk[4]; };

__global__ void __cluster_dims__(2, 1, 1) __launch_bounds__(384, 1)
fused_block_kernel(const __grid_constant__ Maps maps) {
  const CUtensorMap& m_x = maps.m[0];
  extern __shared__ __align__(1024) unsigned char smem_raw[];
  const uint32_t sb = smem_u32(smem_raw);
  const int tid = threadIdx.x;
  const int warp = __shfl_sync(0xffffffffu, tid >> 5, 0);
  const int lane = tid & 31;
  const int b = blockIdx.x;
  const int r = b & 1;
  int grp, mem;
  {
    const int cl = b >> 1;
    if (cl < 4) { grp = 15; mem = cl; }
    else if (cl < 36) { grp = (cl - 4) & 7; mem = (cl - 4) >> 3; }
    else { mem = ((cl - 36) * 37) >> 8; grp = 8 + (cl - 36) - 7 * mem; }
  }
  const int p = ((grp >> 1) & 2) | (mem >> 1);
  const int ti = ((grp & 3) | ((grp >> 1) & 4)) * 2 + (mem & 1);
  const int j = 2 * p + r;

  if (warp < 4) {
    if (elect_one()) {
      if (warp == 0) prefetch_map(&m_x);
      const uint32_t bar = sb + B_XFULL + warp * 8;
      mbar_init(bar, 1); mbar_init(bar + 32, 1);
      mbar_expect_tx(bar, 16384); mbar_expect_tx(bar + 32, 16384);
      asm volatile("fence.mbarrier_init.release.cluster;" ::: "memory");
      fence_async_smem();
#pragma unroll
      for (int q = 0; q < 4; q++) {
        const int wg = q >> 1, kb = warp * 2 + (q & 1);
        tma_load(sb + OFF_XN + kb * 16384 + wg * 8192, &m_x, kb * 64, ti * 128 + wg * 64, bar + wg * 32);
      }
    }
  } else {
    if (lane == 0) {
      if (warp == 8) prefetch_map(&maps.m[1]);
      const int w = warp - 4;
      if (w < 6) { mbar_init(sb + B_FULL + w * 8, 1); mbar_init(sb + B_EMPTY + w * 8, 2); mbar_init(sb + B_FREE + w * 8, 2); }
      if (w >= 3) mbar_init(w == 3 ? sb + B_DR : sb + B_GS + (w - 4) * 8, w == 3 ? 8 : w < 6 ? 2 : 1);
      if (w < 5) {
        mbar_init(sb + B_PF + w * 8, 1);
        mbar_expect_tx(sb + B_PF + w * 8, 16384);
      } else if (w == 6) {
        mbar_init(sb + B_KVD, 8); mbar_init(sb + B_KVOK, 1);
        asm volatile("st.shared.u32 [%0], %1;" ::"r"(sb + OFF_TILE), "r"(ti * 8 + r * 4 + p) : "memory");
      } else if (w == 7) { mbar_init(sb + B_EPOCH, 1); mbar_init(sb + B_PF + 40, 1); }
      asm volatile("fence.mbarrier_init.release.cluster;" ::: "memory");
    }
    if (warp == 9) asm volatile("st.shared.v2.u32 [%0], {%1, %1};" ::"r"(sb + OFF_ONES + lane * 8), "r"(0x3f803f80u) : "memory");
    fence_async_smem();
  }
  __syncthreads();
  asm volatile("barrier.cluster.arrive.relaxed.aligned;" ::: "memory");

  if (warp >= 8) {
    asm volatile("setmaxnreg.dec.sync.aligned.u32 24;");
    int budget = SPIN_LIMIT;
    if (warp == 8 || warp == 11) {
      const int par = warp & 1;
      if (elect_one()) {
#pragma unroll 1
        for (int n = par; n < NSLOT; n += 2) {
          if (n == 2 + par) mbar_wait(sb + B_XFULL + 16, 0, budget);
          const uint32_t bar = sb + B_FULL + n * 8, dst = sb + OFF_RING + n * 16384;
          mbar_expect_tx(bar, 16384);
          tma_load(dst, &maps.m[1], 512 + 64 * j, n * 64, bar);
          tma_load(dst + 8192, &maps.m[1], 1024 + 64 * j, n * 64, bar);
        }
      }
      __syncwarp();
      const uint2 ent = __ldg(reinterpret_cast<const uint2*>(g_boxes.e[j][2 * lane + par]));
      int slot = par, ph = 0;
#pragma unroll 1
      for (int l = 3; l < 30; l++) {
        const uint32_t e0 = __shfl_sync(0xffffffffu, ent.x, l), e1 = __shfl_sync(0xffffffffu, ent.y, l);
        const uint32_t bar = sb + B_FULL + slot * 8;
        mbar_wait(bar + 48, ph, budget);
        if (elect_one()) {
          if (l == 7) {
            mbar_arrive(bar);
          } else {
            const uint32_t dst = sb + OFF_RING + slot * 16384;
            mbar_expect_tx(bar, 16384);
            tma_load(dst, &maps.m[e0 >> 22], e0 & 2047, (e0 >> 11) & 2047, bar);
            tma_load(dst + 8192, &maps.m[e1 >> 22], e1 & 2047, (e1 >> 11) & 2047, bar);
            if (l >= 4 && l < 13) {
              tma_load(dst + 4096, &maps.m[7], e0 & 2047, (e0 >> 11) & 2047, bar);
              tma_load(dst + 12288, &maps.m[7 + r], (e1 & 2047) + 64 * r, (e1 >> 11) & 2047, bar);
            }
          }
        }
        slot += 2;
        if (slot >= NSLOT) { slot -= NSLOT; ph ^= 1; }
      }
    } else if (warp == 9) {
      unsigned e = 0;
      if (lane == 0) {
        e = g_epoch[b * 8] + 1;
        g_epoch[b * 8] = e;
        asm volatile("st.shared.u32 [%0], %1;" ::"r"(sb + OFF_EPOCHV), "r"(e) : "memory");
        mbar_arrive(sb + B_EPOCH);
      }
      e = __shfl_sync(0xffffffffu, e, 0);
      if (lane < 17) reinterpret_cast<float4*>(&g_kv[(e + 1) & 1][j][ti * 68])[lane] = make_float4(0.f, 0.f, 0.f, 0.f);
      if (lane == 0) {
        mbar_wait(sb + B_KVD, 0, budget);
        asm volatile("red.release.gpu.global.add.u32 [%0], 1;" ::"l"(&g_kvcnt[j * 32]) : "memory");
      }
      __syncwarp();
      if (elect_one()) {
        mbar_wait(sb + B_DR, 0, budget);
#pragma unroll 1
        for (int ps = 0; ps < 2; ps++) {
          uint4* dst = g_inbox[ti * 8 + r * 4 + ((p + 1 + ps) & 3)][ps];
          bulk_store(dst, sb + OFF_XN + (ps + 1) * 16384, 16384);
        }
        asm volatile("cp.async.bulk.commit_group;" ::: "memory");
#pragma unroll 1
        for (int q = 0; q < 2; q++) {
          const uint4* src = g_inbox[ti * 8 + r * 4 + p][q];
          mbar_wait(sb + B_GS + q * 8, 0, budget);
          mbar_expect_tx(sb + B_GL + q * 8, 16384);
          bulk_load(sb + OFF_XN + q * 6 * 16384, src, 16384, sb + B_GL + q * 8);
        }
        asm volatile("cp.async.bulk.wait_group.read 0;" ::: "memory");
      }
    } else {
      if (lane >= 2 && lane < 9) prefetch_map(&maps.m[lane]);
      if (elect_one()) {
        if (r == 1) {
          mbar_wait(sb + B_EPOCH, 0, budget);
          unsigned e;
          asm volatile("ld.shared.u32 %0, [%1];" : "=r"(e) : "r"(sb + OFF_EPOCHV) : "memory");
          poll_ge(&g_kvcnt[(j - 1) * 32], 16u * e, budget);
          poll_ge(&g_kvcnt[j * 32], 16u * e, budget);
          mbar_arrive(sb + B_KVOK);
        }
        mbar_wait(sb + B_XD7, 0, budget);
        mbar_expect_tx(sb + B_PF + 40, 16384);
        tma_load(sb + OFF_XN + 7 * 16384, &m_x, 256 * r + 64 * p, ti * 128, sb + B_PF + 40);
        tma_load(sb + OFF_XN + 7 * 16384 + 8192, &m_x, 256 * r + 64 * p, ti * 128 + 64, sb + B_PF + 40);
      }
    }
  } else {
    asm volatile("setmaxnreg.inc.sync.aligned.u32 240;");
    const int wg = warp >> 2, w4 = warp & 3;
    Ctx c;
    c.sb = sb;
    c.da = maps.dk[0] + (((sb & 0x3ffff) >> 4) + wg * 512);
    c.db = maps.dk[1] + (((sb & 0x3ffff) + OFF_RING) >> 4);
    c.el = (tid & 127) == 0; c.budget = SPIN_LIMIT;
    asm("mapa.shared::cluster.u32 %0, %1, %2;" : "=r"(c.rsb) : "r"(sb), "r"(r ^ 1));
    const bool el = c.el;
    auto lane_off = [](int t) { return (uint32_t)((((t >> 5) & 3) * 16 + ((t >> 3) & 1) * 8 + (t & 7)) * 128 + ((((t >> 4) & 1) ^ (t & 7)) << 4)); };
    const uint32_t loff = lane_off(tid);
    float A0[64], A1[64], F[128];
    float r0, r1;
    uint32_t H[48], Hp[48], L[48];

    {
      uint32_t a[128];
      const uint32_t xt = sb + OFF_XN + wg * 8192;
      float s[4][4];
#pragma unroll
      for (int i = 0; i < 4; i++) { s[i][0] = s[i][1] = s[i][2] = s[i][3] = 0.f; }
#pragma unroll
      for (int q = 0; q < 4; q++) {
        mbar_wait(sb + B_XFULL + wg * 32 + q * 8, 0, c.budget);
#pragma unroll
        for (int ks = 8 * q; ks < 8 * q + 8; ks++) ldsm4(a + 4 * ks, xt + (loff ^ ((ks & 3) << 5)) + (ks >> 2) * 16384);
#pragma unroll
        for (int ks = 8 * q; ks < 8 * q + 8; ks++) mma_rowsum(s[ks & 3], a + 4 * ks);
      }
      const float mean0 = ((s[0][0] + s[1][0]) + (s[2][0] + s[3][0])) * (1.f / 512.f);
      const float mean1 = ((s[0][2] + s[1][2]) + (s[2][2] + s[3][2])) * (1.f / 512.f);
      const uint32_t m0 = pack2(mean0, mean0), m1 = pack2(mean1, mean1);
      const float dl0 = mean0 - bf_lo(m0), dl1 = mean1 - bf_lo(m1);
      auto centre = [&](int st) {
#pragma unroll
        for (int i = 16 * st; i < 16 * st + 16; i++) a[i] = sub2(a[i], (i & 1) ? m1 : m0);
        pin<16>(a + 16 * st);
      };
      centre(0);
      float ss0 = 0.f, ss1 = 0.f;
      auto prework = [&](int st) {
        uint32_t q0 = 0, q1 = 0;
#pragma unroll
        for (int kk = 0; kk < 4; kk++) {
          const uint32_t* q = a + 16 * st + 4 * kk;
          stsm4(xt + (loff ^ (kk << 5)) + st * 16384, q);
          q0 = fma2(q[0], q[0], q0); q1 = fma2(q[1], q[1], q1);
          q0 = fma2(q[2], q[2], q0); q1 = fma2(q[3], q[3], q1);
        }
        ss0 += bf_lo(q0) + bf_hi(q0);
        ss1 += bf_lo(q1) + bf_hi(q1);
      };
#define C0_STAGE(ST)                                                                                   \
      {                                                                                                \
        if (ST == 0) wait_full<0>(c);                                                                  \
        wg_fence();                                                                                    \
        wgmma_rs_n128<ST != 0, (ST % NSLOT) * 1024>(A0, a + 16 * ST, c.db);                            \
        wgmma_rs_n128<1, (ST % NSLOT) * 1024 + 128>(A0, a + 16 * ST + 4, c.db);                        \
        wgmma_rs_n128<1, (ST % NSLOT) * 1024 + 256>(A0, a + 16 * ST + 8, c.db);                        \
        wgmma_rs_n128<1, (ST % NSLOT) * 1024 + 384>(A0, a + 16 * ST + 12, c.db);                       \
        wg_commit();                                                                                   \
        wait_full<ST + 1>(c);                                                                          \
        if (ST >= 1) { wg_wait<1>(); release<(ST >= 1 ? ST - 1 : 0)>(c); }                             \
        if (ST == 1) { pin<16>(a); prework(0); }                                                       \
        if (ST < 7) { centre(ST < 7 ? ST + 1 : 0); prework(ST < 7 ? ST + 1 : 0); }                     \
        if (ST == 6) { fence_async_smem(); wg_bar(wg); }                                               \
      }
      C0_STAGE(0) C0_STAGE(1) C0_STAGE(2) C0_STAGE(3) C0_STAGE(4) C0_STAGE(5) C0_STAGE(6) C0_STAGE(7)
#undef C0_STAGE
      float v0 = ss0, v1 = ss1;
      v0 += __shfl_xor_sync(0xffffffffu, v0, 1); v1 += __shfl_xor_sync(0xffffffffu, v1, 1);
      v0 += __shfl_xor_sync(0xffffffffu, v0, 2); v1 += __shfl_xor_sync(0xffffffffu, v1, 2);
      r0 = rsqrtf(fmaxf(v0 * (1.f / 512.f) - dl0 * dl0, 0.f) + 1e-5f);
      r1 = rsqrtf(fmaxf(v1 * (1.f / 512.f) - dl1 * dl1, 0.f) + 1e-5f);
      asm volatile("" : "+f"(r0), "+f"(r1));
      asm volatile("barrier.cluster.wait.aligned;" ::: "memory");
      wg_wait<0>(); release<7>(c); pinf<64>(A0);
      issue_f<8, 0, 1>(F, c);
      issue_f<9, 1, 2>(F, c);
    }
    {
      uint32_t pk[16];
      phi_pack<8>(A0, pk, r0, r1);
      retire<8>(c);
      issue_f<10, 2, 3>(F, c);
      phi_pack<8>(A0 + 16, pk + 8, r0, r1);
      retire<9>(c);
      issue_f<11, 3, 1>(F, c);
      wait_full<14>(c); wait_full<15>(c);
      mbar_arrive_if(sb + B_EMPTY + (wg ? 14 % NSLOT : 15 % NSLOT) * 8, el);
      const uint32_t dof = sb + slot_off<14>() + wg * 16384;
      auto put_v = [&](int ng) {
        uint32_t q[4];
#pragma unroll
        for (int e = 0; e < 4; e++) {
          const float rr = (e & 1) ? r1 : r0;
          q[e] = pack2(A0[32 + 8 * ng + 2 * e] * rr, A0[33 + 8 * ng + 2 * e] * rr);
        }
        stsm4(dof + 8192 + (loff ^ (ng << 5)), q);
      };
#pragma unroll
      for (int ng = 0; ng < 4; ng++) stsm4(dof + (loff ^ (ng << 5)), pk + 4 * ng);
      put_v(0); put_v(1);
      retire<10>(c);
      issue_f<12, 4, 2>(F, c);
      put_v(2); put_v(3);
      fence_async_smem();
      wg_bar(wg);
      retire<11>(c);
      float KV[32], Z[4];
      const uint64_t dp = c.db + (uint32_t)(wg * 1024 + 2048);
      const uint64_t d1 = maps.dk[3] + (((sb & 0x3ffff) + OFF_RING) >> 4);
      constexpr int O1 = (OFF_ONES - OFF_RING) >> 4;
      wg_fence();
      wgmma_ss_n64_t11<0, 0, 512>(KV, dp, dp);          wgmma_ss_n8_t11<0, 0, O1>(Z, dp, d1);
      wgmma_ss_n64_t11<1, 128, 640>(KV, dp, dp);        wgmma_ss_n8_t11<1, 128, O1>(Z, dp, d1);
      wgmma_ss_n64_t11<1, 256, 768>(KV, dp, dp);        wgmma_ss_n8_t11<1, 256, O1>(Z, dp, d1);
      wgmma_ss_n64_t11<1, 384, 896>(KV, dp, dp);        wgmma_ss_n8_t11<1, 384, O1>(Z, dp, d1);
      wg_commit();
      issue_f<13, 5, 1>(F, c);
      retire<12>(c);
      mbar_arrive_if(sb + B_EMPTY + (wg ? 15 % NSLOT : 14 % NSLOT) * 8, el);
      pinf<32>(KV); pinf<4>(Z);
      issue_f<16, 6>(F, c);
      mbar_wait(sb + B_EPOCH, 0, c.budget);
      float k8[8];
#pragma unroll
      for (int i = 0; i < 8; i++) k8[i] = w4 == 0 ? KV[i] : w4 == 1 ? KV[8 + i] : w4 == 2 ? KV[16 + i] : KV[24 + i];
      const int lane = fresh_tid() & 31, g = lane >> 2, cc = lane & 3;
      const float zz = cc ? Z[2] : Z[0];
      const uint32_t tile = lds32(sb + OFF_TILE);
      float* dst = &g_kv[lds32(sb + OFF_EPOCHV) & 1][2 * (tile & 3) + r][w4 * 272 + g];
      const int turn = 7 + ((((tile >> 3) * 2 + wg) * 9) >> 5);
      retire<13>(c);
      loop_f<17, 7, 9>(F, c, 16 % NSLOT, wg, [&](int f) {
        if (f == turn) {
#pragma unroll
          for (int i = 0; i < 4; i++)
            asm volatile("red.relaxed.gpu.global.add.v2.f32 [%0], {%1, %2};" ::"l"(dst + g * 15 + 2 * cc + (i & 1) * 128 + (i >> 1) * 8),
                         "f"(k8[2 * i]), "f"(k8[2 * i + 1]) : "memory");
          if (cc < 2) asm volatile("red.relaxed.gpu.global.add.f32 [%0], %1;" ::"l"(dst + 256 + cc * 8), "f"(zz) : "memory");
          __syncwarp();
          mbar_arrive_if(sb + B_KVD, lane == 0);
        }
      });
    }
    wg_wait<0>(); release<25>(c); pinf<128>(F);
    gu_math(F, H, r0, r1);
    issue_ss<26, 0>(A1, c);
    issue_ss<27, 1, 2>(A1, c);
    if (r == 0) gu_math(F + 64, L, r0, r1);
    else phi_pack<8>(F + 64, L, r0, r1);
    retire<26>(c);
    issue_ss<28, 2, 1>(A1, c);
    if (r) phi_pack<8>(F + 80, L + 8, r0, r1);
    retire<27>(c);
    issue_ss<29, 3>(A1, c);
    if (r) phi_pack<8>(F + 96, L + 16, r0, r1);
    retire<28>(c);
    issue_ss<30, 4>(A1, c);
    if (r) phi_pack<8>(F + 112, L + 24, r0, r1);
    pin<32>(L);
    retire<29>(c);
    issue_ss<31, 5>(A1, c);
    float2 kvv[8]; float zv;
    if (r) {
      mbar_wait(sb + B_KVOK, 0, c.budget);
      const int t = fresh_tid() & 127;
      const float* src = &g_kv[lds32(sb + OFF_EPOCHV) & 1][2 * (lds32(sb + OFF_TILE) & 3)][0];
#pragma unroll
      for (int h = 0; h < 8; h++)
        asm volatile("ld.relaxed.gpu.global.v2.f32 {%0, %1}, [%2];" : "=f"(kvv[h].x), "=f"(kvv[h].y) : "l"(src + h * 272 + 2 * t) : "memory");
      asm volatile("ld.relaxed.gpu.global.f32 %0, [%1];" : "=f"(zv) : "l"(src + (t >> 4) * 272 + 256 + (t & 15)) : "memory");
    }
    retire<30>(c);
    loop_ss<32, 6, 2, false>(A1, c);
    issue_ss<34, 0>(A0, c);
    wg_wait<1>(); release<33>(c); pinf<64>(A1);
    issue_ss<35, 1, 2>(A0, c);
    gu_math(A1, H + 16, r0, r1);
    wg_wait<1>(); release<34>(c);
    const uint32_t kvb = sb + OFF_XN + wg * 8192;
    const uint32_t foff = (fresh_tid() >> 5) * 1536 + fresh_tid() * 16;
    {
      float oa[48], ob[48];
      const uint64_t dkv = maps.dk[2] + (((sb & 0x3ffff) >> 4) + wg * 512);
      issue_ss<36, 2, 1>(A0, c);
      if (r) {
        const int t = fresh_tid() & 127, d = t >> 3, e = (t & 7) * 2;
        const uint32_t o = kvb + (e >> 3) * 256 + (d >> 3) * 128 + (d & 7) * 16 + (e & 7) * 2;
#pragma unroll
        for (int h = 0; h < 8; h++) asm volatile("st.shared.u32 [%0], %1;" ::"r"(o + h * 768), "r"(pack2(kvv[h].x, kvv[h].y)) : "memory");
        const uint32_t zz = pack2(zv, zv);
        sts128(kvb + (t >> 4) * 768 + 512 + (t & 15) * 16, zz, zz, zz, zz);
        fence_async_smem();
        wg_bar(wg);
      }
      wg_wait<1>(); release<35>(c); free_block<1>(c);
      if (r) o_issue<0>(oa, L, dkv);
      issue_ss<37, 3>(A0, c);
      wg_wait<1>(); release<36>(c); free_block<2>(c);
      pinf<48>(oa);
      if (r) o_finish(oa, L);
      pin<16>(L);
      if (r) o_issue<4>(ob, L + 16, dkv);
      issue_ss<38, 4>(A0, c);
      send_frag<0>(H, foff, c);
      retire<37>(c); free_block<3>(c);
      pinf<48>(ob);
      if (r) o_finish(ob, L + 16);
      pin<16>(L + 16);
    }
    loop_ss<39, 5, 1, true>(A0, c);
    issue_ss<40, 6>(A0, c);
    send_frag<1>(H + 16, foff, c);
    retire<39>(c); free_block<5>(c);
    loop_ss<41, 7, 1, false>(A0, c);
    float P0[32], P1[32];
    auto inbox_of = [&](int ps) {
      const uint32_t tile = lds32(sb + OFF_TILE);
      return &g_inbox[(tile & ~3u) | ((tile + 1 + ps) & 3)][ps][(fresh_tid() >> 5) * 96 + fresh_tid()];
    };
    const uint32_t fr = sb + OFF_XN + foff;
    {
      float PA[64];
      issue_rs128<42, 1>(PA, H, c);
      send_frag<2>(L, foff, c);
      retire<41>(c);
      mbar_arrive_if(sb + B_XD7, el);
      pinf<64>(A0);
      issue_rs128<43, 0, 2>(PA, H + 16, c);
      gu_math(A0, H + 32, r0, r1);
      retire<42>(c);
      issue_rs128<44, 0, 1>(PA, L, c);
      mbar_wait(sb + B_PF, 0, c.budget);
      lds_frag(Hp, fr + 16384);
      retire<43>(c);
      if (r) send_frag<3>(L + 16, foff, c);
      issue_rs128<45, 0>(PA, Hp, c);
      retire<44>(c);
      issue_rs128<46, 0>(PA, H + 32, c);
      mbar_wait(sb + B_PF + 8, 0, c.budget);
      lds_frag(Hp + 16, fr + 2 * 16384);
      retire<45>(c);
      send_frag<4>(H + 32, foff, c);
      issue_rs128<47, 0>(PA, Hp + 16, c);
      if (r == 0) {
        mbar_wait(sb + B_PF + 16, 0, c.budget);
        lds_frag(L + 16, fr + 3 * 16384);
      }
      pin<16>(L + 16);
      retire<46>(c);
      issue_rs128<48, 0>(PA, L + 16, c);
      mbar_wait(sb + B_PF + 24 - 8 * r, 0, c.budget);
      lds_frag(L + 32, fr + (4 - r) * 16384);
      retire<47>(c);
      trail<4>(wg == 1);
      issue_rs128<49, 0>(PA, L + 32, c);
      lead<4>(wg == 0);
      mbar_wait(sb + B_PF + 32, 0, c.budget);
      lds_frag(Hp + 32, fr + 5 * 16384);
      retire<48>(c);
      issue_rs128<50, 0>(PA, Hp + 32, c);
      retire<49>(c);
      const uint32_t tag = lds32(sb + OFF_EPOCHV) & 1;
      wg_wait<0>(); release<50>(c);
      pinf<64>(PA);
      stage_pkts(PA, fr + 16384, tag);
      stage_pkts(PA + 32, fr + 2 * 16384, tag);
    }
    issue_rs2<51, 1, 0, 2>(P0, H, P0, H + 16, c);
    fence_async_smem();
    __syncwarp();
    mbar_arrive_if(sb + B_DR, (fresh_tid() & 31) == 0);
    body_rs2<52, 0, 0, 1>(P0, L, P0, Hp, c);
    body_rs2<53, 0, 0>(P0, H + 32, P0, Hp + 16, c);
    body_rs2<54, 0, 0, 2>(P0, L + 16, P0, L + 32, c);
    wg_fence();
    box_rs<55, 0, 0>(P0, Hp + 32, c.db);
    wg_commit();
    box_rs<55, 1, 1>(P1, H, c.db);
    wait_full<56>(c);
    wg_fence();
    box_rs<56, 0, 0>(P1, H + 16, c.db);
    wg_commit();
    wg_wait<1>();
    pinf<32>(P0);
    const uint32_t par = lds32(sb + OFF_EPOCHV) & 1;
    uint32_t w0[16], w1[16];
    make_pkts(P0, w0, par);
    send_pkts(inbox_of(2), w0);
    mbar_arrive_if(sb + B_GS, el);
    const uint32_t tile = lds32(sb + OFF_TILE), loff2 = lane_off(fresh_tid());
    const uint4* inb = &g_inbox[tile][0][(fresh_tid() >> 5) * 96 + fresh_tid()];
    const uint32_t ot = sb + OFF_XN + 7 * 16384 + wg * 8192;
    float S[32];
    wg_fence();
    box_rs<56, 1, 0>(P1, L, c.db);
    wg_commit();
    issue_rs2<57, 0, 0, 2>(P1, Hp, P1, H + 32, c);
    issue_rs2<58, 0, 0, 3>(P1, Hp + 16, P1, L + 16, c);
    mbar_arrive_if(sb + B_GS + 8, el);
    wg_wait<1>();
    mbar_wait(sb + B_PF + 40, 0, c.budget);
#pragma unroll
    for (int ng = 0; ng < 4; ng++) {
      uint32_t q[4];
      ldsm4(q, ot + (loff2 ^ (ng << 5)));
#pragma unroll
      for (int e = 0; e < 4; e++) { S[8 * ng + 2 * e] = bf_lo(q[e]); S[8 * ng + 2 * e + 1] = bf_hi(q[e]); }
    }
    pinf<32>(S);
    issue_rs2<59, 0, 0, 1>(P1, L + 32, P1, Hp + 32, c);
    uint32_t w2[16];
    mbar_wait(sb + B_GL, 0, c.budget);
    lds_frag(w0, fr);
    gather_check(w0, inb, par, c.budget);
    gather_issue(w2, inb + 2048);
    mbar_wait(sb + B_GL + 8, 0, c.budget);
    lds_frag(w1, fr + 6 * 16384);
    gather_check(w1, inb + 1024, par, c.budget);
#pragma unroll
    for (int i = 0; i < 16; i++) w0[i] = add2(w0[i], w1[i]);
    pin<16>(w0);
    wg_wait<0>();
    pinf<32>(P1);
#pragma unroll
    for (int i = 0; i < 32; i++) S[i] += P1[i];
    pinf<32>(S);
    const int t_ = fresh_tid(), rr = (t_ >> 3) & 3, ch = t_ & 7;
    uint4* odst = maps.out + ((tile >> 3) * 128 + (t_ >> 5) * 16 + rr) * 64 + (tile & 7) * 8 + ch;
    uint32_t osrc = sb + OFF_XN + 7 * 16384 + (t_ >> 5) * 2048 + rr * 128;
    asm volatile("" : "+l"(odst), "+r"(osrc));
    gather_check(w2, inb + 2048, par, c.budget);
#pragma unroll
    for (int i = 0; i < 16; i++) {
      const uint32_t t = add2(w0[i], w2[i]);
      S[2 * i] += bf_lo(t); S[2 * i + 1] += bf_hi(t);
    }
#pragma unroll
    for (int ng = 0; ng < 4; ng++) {
      uint32_t q[4];
#pragma unroll
      for (int e = 0; e < 4; e++)
        q[e] = pack2(S[8 * ng + 2 * e], S[8 * ng + 2 * e + 1]);
      stsm4(ot + (loff2 ^ (ng << 5)), q);
    }
    __syncwarp();
    {
#pragma unroll
      for (int q = 0; q < 4; q++) {
        uint32_t w[4];
        lds128(w, osrc + q * 512 + ((ch ^ (rr + 4 * (q & 1))) << 4));
        asm volatile("st.global.v4.u32 [%0], {%1,%2,%3,%4};" ::"l"(odst + q * 256), "r"(w[0]), "r"(w[1]), "r"(w[2]), "r"(w[3]) : "memory");
      }
    }
  }
}

typedef CUresult (*EncodeFn)(CUtensorMap*, CUtensorMapDataType, cuuint32_t, void*, const cuuint64_t*, const cuuint64_t*,
                             const cuuint32_t*, const cuuint32_t*, CUtensorMapInterleave, CUtensorMapSwizzle,
                             CUtensorMapL2promotion, CUtensorMapFloatOOBfill);

CUtensorMap make_map(EncodeFn enc, const void* ptr, uint64_t cols, uint64_t rows, uint32_t box_rows = 64) {
  CUtensorMap m;
  cuuint64_t dims[2] = {cols, rows};
  cuuint64_t strides[1] = {cols * 2};
  cuuint32_t box[2] = {64, box_rows};
  cuuint32_t es[2] = {1, 1};
  enc(&m, CU_TENSOR_MAP_DATA_TYPE_BFLOAT16, 2, const_cast<void*>(ptr), dims, strides, box, es, CU_TENSOR_MAP_INTERLEAVE_NONE,
      CU_TENSOR_MAP_SWIZZLE_128B, CU_TENSOR_MAP_L2_PROMOTION_L2_128B, CU_TENSOR_MAP_FLOAT_OOB_FILL_NONE);
  return m;
}

}

extern "C" void kernel_launch(void* const* d_in, const int* in_sizes, int n_in, void* d_out, int out_size) {
  (void)in_sizes; (void)n_in; (void)out_size;
  static EncodeFn enc = nullptr;
  if (!enc) {
    void* fn = nullptr;
    cudaDriverEntryPointQueryResult st;
    cudaGetDriverEntryPoint("cuTensorMapEncodeTiled", &fn, cudaEnableDefault, &st);
    enc = (EncodeFn)fn;
    cudaFuncSetAttribute(fused_block_kernel, cudaFuncAttributeMaxDynamicSharedMemorySize, SMEM_BYTES);
  }
  Maps maps;
  maps.m[0] = make_map(enc, d_in[0], 512, 2048);
  maps.m[1] = make_map(enc, d_in[1], 1536, 512);
  maps.m[2] = make_map(enc, d_in[4], 1792, 512);
  maps.m[3] = make_map(enc, d_in[5], 1792, 512);
  maps.m[4] = make_map(enc, d_in[6], 512, 1792);
  maps.m[5] = make_map(enc, d_in[2], 512, 512);
  maps.m[6] = make_map(enc, d_in[4], 1792, 512, 32);
  maps.m[7] = make_map(enc, d_in[5], 1792, 512, 32);
  maps.m[8] = make_map(enc, d_in[1], 1536, 512, 32);
  maps.out = (uint4*)d_out;
  maps.dk[0] = (1ull << 16) | (64ull << 32) | (1ull << 62);
  maps.dk[1] = (512ull << 16) | (64ull << 32) | (1ull << 62);
  maps.dk[2] = (8ull << 16) | (16ull << 32);
  maps.dk[3] = (8ull << 16) | (8ull << 32);
  fused_block_kernel<<<NCTA, 384, SMEM_BYTES>>>(maps);
}
```
